```python
import torch

def _softmax(x, axis=-1):
    return torch.softmax(x, dim=axis)

def _gelu(x):
    return torch.nn.functional.gelu(x, approximate='tanh')

def _silu(x):
    return torch.nn.functional.silu(x)

def _sigmoid(x):
    return torch.sigmoid(x)

def _layernorm(x, axis=-1, eps=1e-05):
    m = x.mean(dim=axis, keepdim=True)
    v = x.var(dim=axis, keepdim=True, unbiased=False)
    return (x - m) / torch.sqrt(v + eps)

def _scatter_add(tgt, idx, src, axis=0):
    return tgt.clone().index_add_(axis, idx, src)

def _segment_sum(src, seg, n):
    out = torch.zeros((n,) + src.shape[1:], dtype=src.dtype)
    return out.index_add_(0, seg, src)

def _pad(x, pw):
    flat = tuple((v for pair in reversed(pw) for v in pair))
    return torch.nn.functional.pad(x, flat)
kernel_name = 'adaLN_cond__ssm_conv_s4d__glu_gated_geglu__prompt'

def setup_inputs():

    _w = lambda a: (lambda t: t.to(torch.bfloat16) if t.is_floating_point() else t)(torch.as_tensor(a))

    def _A_setup():
        Bsz, L, D, N = (1, 2048, 640, 128)
        return {'u': _w((lambda *s: torch.randn(*s, dtype=torch.bfloat16) * 0.05)(Bsz, L, D)), 'log_A_real': _w((lambda *s: torch.randn(*s, dtype=torch.bfloat16) * 3.2)(D, N) * 0.5), 'A_imag': _w((lambda *s: torch.randn(*s, dtype=torch.bfloat16) * 0.05)(D, N) * 3.14), 'C_real': _w((lambda *s: torch.randn(*s, dtype=torch.bfloat16) * 0.4)(D, N) / N ** 0.5), 'C_imag': _w((lambda *s: torch.randn(*s, dtype=torch.bfloat16) * 0.4)(D, N) / N ** 0.5), 'log_dt': _w((lambda *s: torch.randn(*s, dtype=torch.bfloat16) * 0.05)(D) * 0.5 - 4.0), 'D_skip': _w((lambda *s: torch.randn(*s, dtype=torch.bfloat16) * 0.05)(D))}
    _A_in = _A_setup()

    def _B_setup():
        B, S, Dm, Df = (1, 2048, 640, 1728)
        return {'x': _w((lambda *s: torch.randn(*s, dtype=torch.bfloat16) * 0.05)(B, S, Dm)), 'w_gate': _w((lambda *s: torch.randn(*s, dtype=torch.bfloat16) * 0.8)(Dm, Df) * Dm ** (-0.5)), 'w_up': _w((lambda *s: torch.randn(*s, dtype=torch.bfloat16) * 0.8)(Dm, Df) * Dm ** (-0.5)), 'w_down': _w((lambda *s: torch.randn(*s, dtype=torch.bfloat16) * 0.8)(Df, Dm) * Df ** (-0.5))}
    _B_in = _B_setup()
    return {'A_u': _A_in['u'], 'A_log_A_real': _A_in['log_A_real'], 'A_A_imag': _A_in['A_imag'], 'A_C_real': _A_in['C_real'], 'A_C_imag': _A_in['C_imag'], 'A_log_dt': _A_in['log_dt'], 'A_D_skip': _A_in['D_skip'], 'B_x': _B_in['x'], 'B_w_gate': _B_in['w_gate'], 'B_w_up': _B_in['w_up'], 'B_w_down': _B_in['w_down'], 'c': _w((lambda *s: torch.randn(*s, dtype=torch.bfloat16) * 0.2)(1, 640) * 8.0), 'w_mod': _w((lambda *s: torch.randn(*s, dtype=torch.bfloat16) * 0.2)(640, 6 * 640) * 640 ** (-0.5) * 8.0)}

def reference(A_u, A_log_A_real, A_A_imag, A_C_real, A_C_imag, A_log_dt, A_D_skip, B_x, B_w_gate, B_w_up, B_w_down, c, w_mod):

    def _A_ref(u, log_A_real, A_imag, C_real, C_imag, log_dt, D_skip):
        L = u.shape[1]
        dt = torch.exp(log_dt)
        A = -torch.exp(log_A_real) + 1j * A_imag
        C = (C_real + 1j * C_imag) * dt[:, None]
        pos = (lambda x, dt: x.to(dt))(torch.arange(L), log_dt.dtype)
        P = torch.exp((A * dt[:, None])[:, :, None] * pos[None, None, :])
        K = 2.0 * torch.einsum('dn,dnl->dl', C, P).real
        L2 = 2 * L
        u_t = (lambda x, *d: x.permute(*d))(u, 0, 2, 1)
        Kf = (lambda x, *a, **k: torch.fft.rfft(x.float(), *a, **k))(K, L2)
        Uf = (lambda x, *a, **k: torch.fft.rfft(x.float(), *a, **k))(u_t, L2)
        y = (lambda x, *a, **k: torch.fft.irfft(x, *a, **k).to(torch.bfloat16))(Uf * Kf[None, :, :], L2)[:, :, :L]
        y = (lambda x, *d: x.permute(*d))(y, 0, 2, 1)
        return y + u * D_skip[None, None, :]

    def _B_ref(x, w_gate, w_up, w_down):
        g = torch.einsum('bsd,df->bsf', x, w_gate)
        u = torch.einsum('bsd,df->bsf', x, w_up)
        h = _gelu(g) * u
        return torch.einsum('bsf,fd->bsd', h, w_down)
    x = A_u
    mod = (_silu(c) @ w_mod).reshape(c.shape[0], 6, 1, -1)
    sa, ca, ga, sb, cb, gb = (mod[:, 0].clone(), mod[:, 1].clone(), mod[:, 2].clone(), mod[:, 3].clone(), mod[:, 4].clone(), mod[:, 5].clone())
    h = _layernorm(x, axis=-1) * (1 + ca) + sa
    x = x + ga * _A_ref(h, A_log_A_real, A_A_imag, A_C_real, A_C_imag, A_log_dt, A_D_skip)
    h = _layernorm(x, axis=-1) * (1 + cb) + sb
    x = x + gb * _B_ref(h, B_w_gate, B_w_up, B_w_down)
    return x
```

```cpp
#include <cuda_runtime.h>
#include <cuda_bf16.h>
#include <cuda.h>
#include <stdint.h>

template<int TA, int TB> __device__ __forceinline__ void wgmma_ss_n256(float* d, uint64_t da, uint64_t db, int sc) {
    asm volatile("{\n.reg .pred p;\nsetp.ne.b32 p, %130, 0;\n"
        "wgmma.mma_async.sync.aligned.m64n256k16.f32.bf16.bf16 {%0, %1, %2, %3, %4, %5, %6, %7, %8, %9, %10, %11, %12, %13, %14, %15, %16, %17, %18, %19, %20, %21, %22, %23, %24, %25, %26, %27, %28, %29, %30, %31, %32, %33, %34, %35, %36, %37, %38, %39, %40, %41, %42, %43, %44, %45, %46, %47, %48, %49, %50, %51, %52, %53, %54, %55, %56, %57, %58, %59, %60, %61, %62, %63, %64, %65, %66, %67, %68, %69, %70, %71, %72, %73, %74, %75, %76, %77, %78, %79, %80, %81, %82, %83, %84, %85, %86, %87, %88, %89, %90, %91, %92, %93, %94, %95, %96, %97, %98, %99, %100, %101, %102, %103, %104, %105, %106, %107, %108, %109, %110, %111, %112, %113, %114, %115, %116, %117, %118, %119, %120, %121, %122, %123, %124, %125, %126, %127}, %128, %129, p, 1, 1, %131, %132;\n}\n"
        : "+f"(d[0]), "+f"(d[1]), "+f"(d[2]), "+f"(d[3]), "+f"(d[4]), "+f"(d[5]), "+f"(d[6]), "+f"(d[7]), "+f"(d[8]), "+f"(d[9]), "+f"(d[10]), "+f"(d[11]), "+f"(d[12]), "+f"(d[13]), "+f"(d[14]), "+f"(d[15]), "+f"(d[16]), "+f"(d[17]), "+f"(d[18]), "+f"(d[19]), "+f"(d[20]), "+f"(d[21]), "+f"(d[22]), "+f"(d[23]), "+f"(d[24]), "+f"(d[25]), "+f"(d[26]), "+f"(d[27]), "+f"(d[28]), "+f"(d[29]), "+f"(d[30]), "+f"(d[31]), "+f"(d[32]), "+f"(d[33]), "+f"(d[34]), "+f"(d[35]), "+f"(d[36]), "+f"(d[37]), "+f"(d[38]), "+f"(d[39]), "+f"(d[40]), "+f"(d[41]), "+f"(d[42]), "+f"(d[43]), "+f"(d[44]), "+f"(d[45]), "+f"(d[46]), "+f"(d[47]), "+f"(d[48]), "+f"(d[49]), "+f"(d[50]), "+f"(d[51]), "+f"(d[52]), "+f"(d[53]), "+f"(d[54]), "+f"(d[55]), "+f"(d[56]), "+f"(d[57]), "+f"(d[58]), "+f"(d[59]), "+f"(d[60]), "+f"(d[61]), "+f"(d[62]), "+f"(d[63]), "+f"(d[64]), "+f"(d[65]), "+f"(d[66]), "+f"(d[67]), "+f"(d[68]), "+f"(d[69]), "+f"(d[70]), "+f"(d[71]), "+f"(d[72]), "+f"(d[73]), "+f"(d[74]), "+f"(d[75]), "+f"(d[76]), "+f"(d[77]), "+f"(d[78]), "+f"(d[79]), "+f"(d[80]), "+f"(d[81]), "+f"(d[82]), "+f"(d[83]), "+f"(d[84]), "+f"(d[85]), "+f"(d[86]), "+f"(d[87]), "+f"(d[88]), "+f"(d[89]), "+f"(d[90]), "+f"(d[91]), "+f"(d[92]), "+f"(d[93]), "+f"(d[94]), "+f"(d[95]), "+f"(d[96]), "+f"(d[97]), "+f"(d[98]), "+f"(d[99]), "+f"(d[100]), "+f"(d[101]), "+f"(d[102]), "+f"(d[103]), "+f"(d[104]), "+f"(d[105]), "+f"(d[106]), "+f"(d[107]), "+f"(d[108]), "+f"(d[109]), "+f"(d[110]), "+f"(d[111]), "+f"(d[112]), "+f"(d[113]), "+f"(d[114]), "+f"(d[115]), "+f"(d[116]), "+f"(d[117]), "+f"(d[118]), "+f"(d[119]), "+f"(d[120]), "+f"(d[121]), "+f"(d[122]), "+f"(d[123]), "+f"(d[124]), "+f"(d[125]), "+f"(d[126]), "+f"(d[127])
        : "l"(da), "l"(db), "r"(sc), "n"(TA), "n"(TB));
}
template<int TA, int TB> __device__ __forceinline__ void wgmma_ss_n192(float* d, uint64_t da, uint64_t db, int sc) {
    asm volatile("{\n.reg .pred p;\nsetp.ne.b32 p, %98, 0;\n"
        "wgmma.mma_async.sync.aligned.m64n192k16.f32.bf16.bf16 {%0, %1, %2, %3, %4, %5, %6, %7, %8, %9, %10, %11, %12, %13, %14, %15, %16, %17, %18, %19, %20, %21, %22, %23, %24, %25, %26, %27, %28, %29, %30, %31, %32, %33, %34, %35, %36, %37, %38, %39, %40, %41, %42, %43, %44, %45, %46, %47, %48, %49, %50, %51, %52, %53, %54, %55, %56, %57, %58, %59, %60, %61, %62, %63, %64, %65, %66, %67, %68, %69, %70, %71, %72, %73, %74, %75, %76, %77, %78, %79, %80, %81, %82, %83, %84, %85, %86, %87, %88, %89, %90, %91, %92, %93, %94, %95}, %96, %97, p, 1, 1, %99, %100;\n}\n"
        : "+f"(d[0]), "+f"(d[1]), "+f"(d[2]), "+f"(d[3]), "+f"(d[4]), "+f"(d[5]), "+f"(d[6]), "+f"(d[7]), "+f"(d[8]), "+f"(d[9]), "+f"(d[10]), "+f"(d[11]), "+f"(d[12]), "+f"(d[13]), "+f"(d[14]), "+f"(d[15]), "+f"(d[16]), "+f"(d[17]), "+f"(d[18]), "+f"(d[19]), "+f"(d[20]), "+f"(d[21]), "+f"(d[22]), "+f"(d[23]), "+f"(d[24]), "+f"(d[25]), "+f"(d[26]), "+f"(d[27]), "+f"(d[28]), "+f"(d[29]), "+f"(d[30]), "+f"(d[31]), "+f"(d[32]), "+f"(d[33]), "+f"(d[34]), "+f"(d[35]), "+f"(d[36]), "+f"(d[37]), "+f"(d[38]), "+f"(d[39]), "+f"(d[40]), "+f"(d[41]), "+f"(d[42]), "+f"(d[43]), "+f"(d[44]), "+f"(d[45]), "+f"(d[46]), "+f"(d[47]), "+f"(d[48]), "+f"(d[49]), "+f"(d[50]), "+f"(d[51]), "+f"(d[52]), "+f"(d[53]), "+f"(d[54]), "+f"(d[55]), "+f"(d[56]), "+f"(d[57]), "+f"(d[58]), "+f"(d[59]), "+f"(d[60]), "+f"(d[61]), "+f"(d[62]), "+f"(d[63]), "+f"(d[64]), "+f"(d[65]), "+f"(d[66]), "+f"(d[67]), "+f"(d[68]), "+f"(d[69]), "+f"(d[70]), "+f"(d[71]), "+f"(d[72]), "+f"(d[73]), "+f"(d[74]), "+f"(d[75]), "+f"(d[76]), "+f"(d[77]), "+f"(d[78]), "+f"(d[79]), "+f"(d[80]), "+f"(d[81]), "+f"(d[82]), "+f"(d[83]), "+f"(d[84]), "+f"(d[85]), "+f"(d[86]), "+f"(d[87]), "+f"(d[88]), "+f"(d[89]), "+f"(d[90]), "+f"(d[91]), "+f"(d[92]), "+f"(d[93]), "+f"(d[94]), "+f"(d[95])
        : "l"(da), "l"(db), "r"(sc), "n"(TA), "n"(TB));
}
template<int TA, int TB> __device__ __forceinline__ void wgmma_ss_n32(float* d, uint64_t da, uint64_t db, int sc) {
    asm volatile("{\n.reg .pred p;\nsetp.ne.b32 p, %18, 0;\n"
        "wgmma.mma_async.sync.aligned.m64n32k16.f32.bf16.bf16 {%0, %1, %2, %3, %4, %5, %6, %7, %8, %9, %10, %11, %12, %13, %14, %15}, %16, %17, p, 1, 1, %19, %20;\n}\n"
        : "+f"(d[0]), "+f"(d[1]), "+f"(d[2]), "+f"(d[3]), "+f"(d[4]), "+f"(d[5]), "+f"(d[6]), "+f"(d[7]), "+f"(d[8]), "+f"(d[9]), "+f"(d[10]), "+f"(d[11]), "+f"(d[12]), "+f"(d[13]), "+f"(d[14]), "+f"(d[15])
        : "l"(da), "l"(db), "r"(sc), "n"(TA), "n"(TB));
}
template<int TA, int TB> __device__ __forceinline__ void wgmma_ss_n16_f16(float* d, uint64_t da, uint64_t db, int sc) {
    asm volatile("{\n.reg .pred p;\nsetp.ne.b32 p, %10, 0;\n"
        "wgmma.mma_async.sync.aligned.m64n16k16.f32.f16.f16 {%0, %1, %2, %3, %4, %5, %6, %7}, %8, %9, p, 1, 1, %11, %12;\n}\n"
        : "+f"(d[0]), "+f"(d[1]), "+f"(d[2]), "+f"(d[3]), "+f"(d[4]), "+f"(d[5]), "+f"(d[6]), "+f"(d[7])
        : "l"(da), "l"(db), "r"(sc), "n"(TA), "n"(TB));
}
template<int TB> __device__ __forceinline__ void wgmma_rs_n64(float* d, uint32_t a0, uint32_t a1, uint32_t a2, uint32_t a3, uint64_t db, int sc) {
    asm volatile("{\n.reg .pred p;\nsetp.ne.b32 p, %37, 0;\n"
        "wgmma.mma_async.sync.aligned.m64n64k16.f32.bf16.bf16 {%0, %1, %2, %3, %4, %5, %6, %7, %8, %9, %10, %11, %12, %13, %14, %15, %16, %17, %18, %19, %20, %21, %22, %23, %24, %25, %26, %27, %28, %29, %30, %31}, {%32, %33, %34, %35}, %36, p, 1, 1, %38;\n}\n"
        : "+f"(d[0]), "+f"(d[1]), "+f"(d[2]), "+f"(d[3]), "+f"(d[4]), "+f"(d[5]), "+f"(d[6]), "+f"(d[7]), "+f"(d[8]), "+f"(d[9]), "+f"(d[10]), "+f"(d[11]), "+f"(d[12]), "+f"(d[13]), "+f"(d[14]), "+f"(d[15]), "+f"(d[16]), "+f"(d[17]), "+f"(d[18]), "+f"(d[19]), "+f"(d[20]), "+f"(d[21]), "+f"(d[22]), "+f"(d[23]), "+f"(d[24]), "+f"(d[25]), "+f"(d[26]), "+f"(d[27]), "+f"(d[28]), "+f"(d[29]), "+f"(d[30]), "+f"(d[31])
        : "r"(a0), "r"(a1), "r"(a2), "r"(a3), "l"(db), "r"(sc), "n"(TB));
}
template<int TB> __device__ __forceinline__ void wgmma_rs_n32(float* d, uint32_t a0, uint32_t a1, uint32_t a2, uint32_t a3, uint64_t db, int sc) {
    asm volatile("{\n.reg .pred p;\nsetp.ne.b32 p, %21, 0;\n"
        "wgmma.mma_async.sync.aligned.m64n32k16.f32.bf16.bf16 {%0, %1, %2, %3, %4, %5, %6, %7, %8, %9, %10, %11, %12, %13, %14, %15}, {%16, %17, %18, %19}, %20, p, 1, 1, %22;\n}\n"
        : "+f"(d[0]), "+f"(d[1]), "+f"(d[2]), "+f"(d[3]), "+f"(d[4]), "+f"(d[5]), "+f"(d[6]), "+f"(d[7]), "+f"(d[8]), "+f"(d[9]), "+f"(d[10]), "+f"(d[11]), "+f"(d[12]), "+f"(d[13]), "+f"(d[14]), "+f"(d[15])
        : "r"(a0), "r"(a1), "r"(a2), "r"(a3), "l"(db), "r"(sc), "n"(TB));
}

namespace {

constexpr int L_ = 2048, D_ = 640, F_ = 1728, FP_ = 1792;
constexpr int NCTA = 128;
constexpr int SPIN_LIMIT = 50000;

constexpr uint32_t SM_STG   = 0;
constexpr uint32_t SM_Q     = 98304;
constexpr uint32_t Q_STRIDE = 8256;
constexpr uint32_t SM_XT    = 140288;
constexpr uint32_t XT_STRIDE = 4096;
constexpr uint32_t SM_XROW  = 140288;
constexpr uint32_t SM_RED   = 160768;
constexpr uint32_t SM_RING  = 163840;
constexpr uint32_t SM_BAR   = 229376;
constexpr uint32_t SM_MISC  = 229376 + 512;
constexpr uint32_t SM_ST2   = 231424;
constexpr uint32_t SM_TOTAL = 232448;
constexpr uint32_t H1_OFF = 2560, XP_OFF = 8192, XP_PLANE = 10240;
constexpr uint32_t SM_W1 = 123392, XS_OFF = 44032;
constexpr uint32_t CS_OFF = 40960, TIN_OFF = 57344;
constexpr uint32_t A_HALF = 81920, RECV_OFF = 0, OST_OFF = 28672, XSLOT_OFF = 49152;
constexpr int B_XR = 0, B_X = 1, B_WM = 2, B_XS = 3, B_G1 = 4, B_ST = 5, B_STF = 6, B_MOD = 7, B_W = 8, B_CS = 9, B_XD = 10,
              B_FULL = 11, B_EMPTY = 19, B_RDY = 27, B_DEAD = 29, B_OF = 31, B_OE = 35, B_A = 39, B_RECV = 49, B_T = 51, B_TF = 52,
              B_E1 = 53, B_M1 = 54, B_COUNT = 55;
constexpr int C_B1 = 0, C_MOD = 32, C_B2 = 64, C_TILE = 96;

__device__ __align__(128) float2 g_stats1[L_];
__device__ __align__(128) float2 g_stats2[L_];
__device__ __align__(128) float g_sc[3 * 2 * D_];
__device__ float g_ga[D_];
__device__ __align__(128) __nv_bfloat16 g_gb[D_];
__device__ float g_cb1[D_];
__device__ __align__(128) __nv_bfloat16 g_csb[84 * 16];
__device__ __align__(128) float2 g_tab[2 * FP_];
__device__ __align__(1024) __nv_bfloat16 g_xT[D_ * L_];
__device__ __align__(1024) __nv_bfloat16 g_x2T[D_ * L_];
__device__ __align__(1024) __nv_bfloat16 g_x2pT[D_ * L_];
__device__ unsigned int g_ctr[32 * 40];
#define PROF(i)
#define PROFG(i)
#define PROF_DECL
#define PROFT(i)
#define PROF_INIT
#define PROF_DUMP

struct Params {
    const __nv_bfloat16 *x, *logA, *Aim, *Cre, *Cim, *logdt, *Dskip, *wg, *wu, *wd, *c, *wmod;
    __nv_bfloat16* out;
};

__device__ __forceinline__ void wg_fence() { asm volatile("wgmma.fence.sync.aligned;" ::: "memory"); }
__device__ __forceinline__ void wg_commit() { asm volatile("wgmma.commit_group.sync.aligned;" ::: "memory"); }
template <int N> __device__ __forceinline__ void wg_wait() { asm volatile("wgmma.wait_group.sync.aligned %0;" ::"n"(N) : "memory"); }
template <int N> __device__ __forceinline__ void fence_regs(float* d) {
#pragma unroll
    for (int i = 0; i < N; i++) asm volatile("" : "+f"(d[i])::"memory");
}
__device__ __forceinline__ uint64_t mk64(uint32_t lo, uint32_t hi) { uint64_t d; asm("mov.b64 %0, {%1, %2};" : "=l"(d) : "r"(lo), "r"(hi)); return d; }
__device__ __forceinline__ void mbar_init(uint32_t b, uint32_t c) { asm volatile("mbarrier.init.shared::cta.b64 [%0], %1;" ::"r"(b), "r"(c) : "memory"); }
__device__ __forceinline__ void mbar_expect(uint32_t b, uint32_t bytes) { asm volatile("mbarrier.arrive.expect_tx.shared::cta.b64 _, [%0], %1;" ::"r"(b), "r"(bytes) : "memory"); }
__device__ __forceinline__ void mbar_arrive(uint32_t b) { asm volatile("mbarrier.arrive.shared::cta.b64 _, [%0];" ::"r"(b) : "memory"); }
__device__ __forceinline__ void mbar_wait(uint32_t b, uint32_t ph) {
    asm volatile("{\n.reg .pred p, q;\n.reg .u32 n;\nmov.u32 n, 0;\n"
                 "W%=:\nmbarrier.try_wait.parity.shared::cta.b64 p, [%0], %1;\n@p bra D%=;\n"
                 "add.u32 n, n, 1;\nsetp.lt.u32 q, n, %2;\n@q bra W%=;\nD%=:\n}\n" ::"r"(b), "r"(ph), "n"(SPIN_LIMIT) : "memory");
}
__device__ __forceinline__ void bar_sync(int id, int n) { asm volatile("bar.sync %0, %1;" ::"r"(id), "r"(n) : "memory"); }
__device__ __forceinline__ void fence_async_smem() { asm volatile("fence.proxy.async.shared::cta;" ::: "memory"); }
__device__ __forceinline__ void fence_async_gmem() { asm volatile("fence.proxy.async.global;" ::: "memory"); }
__device__ __forceinline__ void bulk_s2g(void* dst, uint32_t src, uint32_t bytes) {
    asm volatile("cp.async.bulk.global.shared::cta.bulk_group [%0], [%1], %2;" ::"l"(dst), "r"(src), "r"(bytes) : "memory");
}
__device__ __forceinline__ void bulk_g2s(uint32_t dst, const void* src, uint32_t bytes, uint32_t bar) {
    asm volatile("cp.async.bulk.shared::cluster.global.mbarrier::complete_tx::bytes [%0], [%1], %2, [%3];" ::"r"(dst), "l"(src), "r"(bytes), "r"(bar) : "memory");
}
__device__ __forceinline__ void tma2d(uint32_t dst, const CUtensorMap* m, int c0, int c1, uint32_t bar) {
    asm volatile("cp.async.bulk.tensor.2d.shared::cluster.global.mbarrier::complete_tx::bytes [%0], [%1, {%3, %4}], [%2];"
                 ::"r"(dst), "l"(m), "r"(bar), "r"(c0), "r"(c1) : "memory");
}
__device__ __forceinline__ void tma2d_pair(uint32_t dst, const CUtensorMap* m, int c0, int c1, uint32_t bar) {
    asm volatile("cp.async.bulk.tensor.2d.shared::cluster.global.mbarrier::complete_tx::bytes.multicast::cluster [%0], [%1, {%3, %4}], [%2], %5;"
                 ::"r"(dst), "l"(m), "r"(bar), "r"(c0), "r"(c1), "h"((unsigned short)3) : "memory");
}
__device__ __forceinline__ void tma3d(uint32_t dst, const CUtensorMap* m, int c0, int c1, int c2, uint32_t bar) {
    asm volatile("cp.async.bulk.tensor.3d.shared::cluster.global.mbarrier::complete_tx::bytes [%0], [%1, {%3, %4, %5}], [%2];"
                 ::"r"(dst), "l"(m), "r"(bar), "r"(c0), "r"(c1), "r"(c2) : "memory");
}
__device__ __forceinline__ void tma_red2d(const CUtensorMap* m, int c0, int c1, uint32_t src) {
    asm volatile("cp.reduce.async.bulk.tensor.2d.global.shared::cta.add.tile.bulk_group [%0, {%2, %3}], [%1];"
                 ::"l"(m), "r"(src), "r"(c0), "r"(c1) : "memory");
}
__device__ __forceinline__ void l2_prefetch(const void* p, uint32_t bytes) {
    asm volatile("cp.async.bulk.prefetch.L2.global [%0], %1;" ::"l"(p), "r"(bytes) : "memory");
}
__device__ __forceinline__ uint32_t lds32(uint32_t a) { uint32_t v; asm volatile("ld.shared.b32 %0, [%1];" : "=r"(v) : "r"(a) : "memory"); return v; }
__device__ __forceinline__ uint32_t lds16(uint32_t a) { uint32_t v; asm volatile("ld.shared.u16 %0, [%1];" : "=r"(v) : "r"(a) : "memory"); return v; }
__device__ __forceinline__ uint4 lds128(uint32_t a) { uint4 v; asm volatile("ld.shared.v4.b32 {%0,%1,%2,%3}, [%4];" : "=r"(v.x), "=r"(v.y), "=r"(v.z), "=r"(v.w) : "r"(a) : "memory"); return v; }
__device__ __forceinline__ void sts32(uint32_t a, uint32_t v) { asm volatile("st.shared.b32 [%0], %1;" ::"r"(a), "r"(v) : "memory"); }
__device__ __forceinline__ void sts16(uint32_t a, uint32_t v) { asm volatile("st.shared.u16 [%0], %1;" ::"r"(a), "h"((unsigned short)v) : "memory"); }
__device__ __forceinline__ void sts128(uint32_t a, uint4 v) { asm volatile("st.shared.v4.b32 [%0], {%1,%2,%3,%4};" ::"r"(a), "r"(v.x), "r"(v.y), "r"(v.z), "r"(v.w) : "memory"); }
__device__ __forceinline__ uint4 ldg128(const void* p) { uint4 v; asm volatile("ld.global.nc.L1::no_allocate.v4.b32 {%0,%1,%2,%3}, [%4];" : "=r"(v.x), "=r"(v.y), "=r"(v.z), "=r"(v.w) : "l"(p)); return v; }
__device__ __forceinline__ uint4 ldcg128(const void* p) { uint4 v; asm volatile("ld.global.cg.v4.b32 {%0,%1,%2,%3}, [%4];" : "=r"(v.x), "=r"(v.y), "=r"(v.z), "=r"(v.w) : "l"(p) : "memory"); return v; }
__device__ __forceinline__ float4 ldca128f(const void* p) { float4 v; asm volatile("ld.global.ca.v4.f32 {%0,%1,%2,%3}, [%4];" : "=f"(v.x), "=f"(v.y), "=f"(v.z), "=f"(v.w) : "l"(p) : "memory"); return v; }
__device__ __forceinline__ float2 ldca64f(const void* p) { float2 v; asm volatile("ld.global.ca.v2.f32 {%0,%1}, [%2];" : "=f"(v.x), "=f"(v.y) : "l"(p) : "memory"); return v; }
__device__ __forceinline__ float ldcgf(const void* p) { float v; asm volatile("ld.global.cg.f32 %0, [%1];" : "=f"(v) : "l"(p) : "memory"); return v; }
__device__ __forceinline__ void mma16816(float* d, uint32_t a0, uint32_t a1, uint32_t a2, uint32_t a3, uint32_t b0, uint32_t b1) {
    asm volatile("mma.sync.aligned.m16n8k16.row.col.f32.bf16.bf16.f32 {%0,%1,%2,%3}, {%4,%5,%6,%7}, {%8,%9}, {%0,%1,%2,%3};"
                 : "+f"(d[0]), "+f"(d[1]), "+f"(d[2]), "+f"(d[3]) : "r"(a0), "r"(a1), "r"(a2), "r"(a3), "r"(b0), "r"(b1));
}
__device__ __forceinline__ float bf_lo(uint32_t v) { return __uint_as_float(v << 16); }
__device__ __forceinline__ float bf_hi(uint32_t v) { return __uint_as_float(v & 0xffff0000u); }
__device__ __forceinline__ uint32_t pack_bf(float lo, float hi) { uint32_t r; asm("cvt.rn.bf16x2.f32 %0, %1, %2;" : "=r"(r) : "f"(hi), "f"(lo)); return r; }
__device__ __forceinline__ uint32_t pack_h(float lo, float hi) { uint32_t r; asm("cvt.rn.f16x2.f32 %0, %1, %2;" : "=r"(r) : "f"(hi), "f"(lo)); return r; }
__device__ __forceinline__ uint32_t hmul_bf(uint32_t a, uint32_t b) { uint32_t r; asm("mul.rn.bf16x2 %0, %1, %2;" : "=r"(r) : "r"(a), "r"(b)); return r; }
__device__ __forceinline__ float bfr(float v) { return __bfloat162float(__float2bfloat16_rn(v)); }
__device__ __forceinline__ float ldbf(const __nv_bfloat16* p) { return __bfloat162float(__ldg(p)); }
__device__ __forceinline__ float tanh_fast(float v) { float r; asm("tanh.approx.f32 %0, %1;" : "=f"(r) : "f"(v)); return r; }

__device__ __forceinline__ void grid_arrive_red(unsigned int* ctr) {
    asm volatile("red.add.release.gpu.global.u32 [%0], 1;" ::"l"(ctr) : "memory");
}
__device__ __forceinline__ float2 ldcg64f(const void* p) { float2 v; asm volatile("ld.global.cg.v2.f32 {%0,%1}, [%2];" : "=f"(v.x), "=f"(v.y) : "l"(p) : "memory"); return v; }
__device__ __forceinline__ void grid_wait(unsigned int* ctr, unsigned int target) {
    unsigned int v;
    int it = 0;
#pragma unroll 1
    do {
        asm volatile("ld.acquire.gpu.global.u32 %0, [%1];" : "=r"(v) : "l"(ctr) : "memory");
    } while (v < target && ++it < SPIN_LIMIT);
}
__device__ __forceinline__ void stg128(void* p, uint32_t a, uint32_t b, uint32_t c, uint32_t d) {
    asm volatile("st.global.v4.b32 [%0], {%1,%2,%3,%4};" ::"l"(p), "r"(a), "r"(b), "r"(c), "r"(d) : "memory");
}
__device__ __forceinline__ float silu_f(float cv) { return __fdividef(cv, 1.0f + __expf(-cv)); }
template <int U> __device__ __forceinline__ void row_mma(float* d, uint64_t da, uint32_t astep, uint64_t db, int n) {
#pragma unroll 1
    for (int k = 0; k < n; k += U) {
        wg_fence();
#pragma unroll
        for (int j = 0; j < U; j++) wgmma_ss_n32<0, 1>(d, da + (k + j) * astep, db + (k + j) * 64, k + j > 0);
        wg_commit();
    }
    wg_wait<0>();
    fence_regs<16>(d);
}

__device__ __forceinline__ uint32_t cmax2(uint2 a, uint2 c) {
    const uint32_t mx = __vmaxu2(__vmaxu2(a.x & 0x7fff7fffu, a.y & 0x7fff7fffu), __vmaxu2(c.x & 0x7fff7fffu, c.y & 0x7fff7fffu));
    return max(mx & 0xffffu, mx >> 16);
}
struct cf { float x, y; };
__device__ __forceinline__ cf cmul(cf a, cf b) { cf r; r.x = fmaf(a.x, b.x, -a.y * b.y); r.y = fmaf(a.x, b.y, a.y * b.x); return r; }
__device__ __forceinline__ cf cmulc(cf a, cf b) { cf r; r.x = fmaf(a.x, b.x, a.y * b.y); r.y = fmaf(a.y, b.x, -a.x * b.y); return r; }
__device__ __forceinline__ cf cexp_dir(float e2, float rev) {
    float r = rev - rintf(rev);
    float ang = r * 6.283185307179586f;
    float m = exp2f(e2);
    cf o; o.x = m * __cosf(ang); o.y = m * __sinf(ang);
    return o;
}
struct KHead { cf w1, w8, w128, cs; float osc; };
__device__ __forceinline__ KHead kgen_head(float ldt, float lar, float aim, float cre, float cim, uint32_t cm) {
    KHead h;
    const float dt = bfr(expf(ldt));
    const float are = -bfr(expf(lar)) * dt, aid = aim * dt;
    const uint32_t E = max(__reduce_max_sync(0xffffffffu, cm) >> 7, 14u);
    const float sc = __uint_as_float((267u - E) << 23);
    h.osc = __uint_as_float((E - 13u) << 23) * (2.0f / 16384.0f) * dt;
    const float e2 = are * 1.4426950408889634f, rv = aid * 0.15915494309189535f;
    h.w1 = cexp_dir(e2, rv); h.w8 = cexp_dir(e2 * 8.f, rv * 8.f); h.w128 = cexp_dir(e2 * 128.f, rv * 128.f);
    h.cs.x = cre * sc; h.cs.y = -cim * sc;
    return h;
}
__device__ __forceinline__ void kgen_body(const KHead& h, uint32_t stg, int t) {
    const int lane = t & 31, wp = t >> 5;
    const uint32_t pre = stg + wp * 8192 + ((lane >> 2) << 4) + ((lane & 3) << 2);
#define KST(r, v) sts32((pre ^ (((r) & 7) << 4)) + (r) * 128, pack_h((v).x, (v).y))
    const cf w16 = cmul(h.w8, h.w8), w2 = cmul(h.w1, h.w1), w256 = cmul(h.w128, h.w128);
    cf c0 = {16384.f, 0.f}, c1 = {h.w8.x * 16384.f, h.w8.y * 16384.f};
    cf r[8];
    KST(40, h.cs);
    r[0] = cmulc(h.cs, h.w1); r[1] = cmulc(h.cs, w2);
#pragma unroll
    for (int i = 2; i < 8; i++) r[i] = cmulc(r[i - 2], w2);
#pragma unroll
    for (int i = 0; i < 8; i++) {
        KST(48 + 2 * i, c0); KST(49 + 2 * i, c1);
        if (i < 7) { c0 = cmul(c0, w16); c1 = cmul(c1, w16); }
        KST(i, r[i]); r[i] = cmulc(r[i], h.w128); KST(8 + i, r[i]);
    }
#pragma unroll
    for (int i = 0; i < 4; i++) { r[2 * i + 1] = cmulc(r[2 * i + 1], h.w128); KST(16 + i, r[2 * i + 1]); }
#pragma unroll
    for (int i = 0; i < 4; i++) { r[2 * i + 1] = cmulc(r[2 * i + 1], h.w128); KST(20 + i, r[2 * i + 1]); }
    cf a0 = cmulc(r[3], h.w128), a1 = cmulc(r[7], h.w128), a2 = cmulc(r[3], w256), a3 = cmulc(r[7], w256);
    KST(24, a0); KST(25, a1); KST(26, a2); KST(27, a3);
    a0 = cmulc(a0, w256); a1 = cmulc(a1, w256); a2 = cmulc(a2, w256); a3 = cmulc(a3, w256);
    KST(28, a0); KST(29, a1); KST(30, a2); KST(31, a3);
#pragma unroll
    for (int i = 0; i < 8; i += 2) {
        a1 = cmulc(a1, w256); a3 = cmulc(a3, w256);
        KST(32 + i, a1); KST(33 + i, a3);
    }
#undef KST
}
constexpr uint32_t TB1 = 5248, TB2 = 8192 - 768;
__device__ __forceinline__ void kgen_tail(const float* d, float osc, uint32_t stg, uint32_t qb, int wg, int t) {
    const int lane = t & 31, wp = t >> 5, g = lane >> 2, t4 = lane & 3;
    const uint32_t tb = stg + TB1;
    if (wp < 3) {
        uint32_t a0, s0, a1, s1;
        if (wp == 0) { a0 = 2 * (1 + g); s0 = 16; a1 = 2 * (129 + g); s1 = 16; }
        else if (wp == 1) { a0 = 2 * ((g < 4) ? 257 + g : 317 + g); s0 = 8; a1 = TB2 + 2 * (385 + 32 * (g >> 1) + (g & 1)); s1 = 4; }
        else { a0 = TB2 + 2 * (513 + 16 * g); s0 = 2; a1 = 0; s1 = 0; }
        const uint32_t p0 = pack_bf(d[0] * osc, d[1] * osc), p1 = pack_bf(d[4] * osc, d[5] * osc);
        const uint32_t p2 = pack_bf(d[2] * osc, d[3] * osc), p3 = pack_bf(d[6] * osc, d[7] * osc);
        a0 += tb + 2 * t4 * s0; a1 += tb + 2 * t4 * s1;
        sts16(a0, p0); sts16(a0 + s0, p0 >> 16); sts16(a0 + 8 * s0, p1); sts16(a0 + 9 * s0, p1 >> 16);
        if (wp < 2) { sts16(a1, p2); sts16(a1 + s1, p2 >> 16); sts16(a1 + 8 * s1, p3); sts16(a1 + 9 * s1, p3 >> 16); }
        else if (lane == 0) sts16(a1, p2);
    }
    bar_sync(1 + wg, 128);
    const bool lo = t < 64;
    const uint32_t w0 = lds32(tb + (lo ? 8 * t : 256 + 4 * t)), w1 = lds32(tb + (lo ? 8 * t + 4 : 260 + 4 * t));
    const uint32_t wm = lds16(tb + (lo ? 8 * t - 2 : 510));
    const uint32_t a1 = lds16(tb + (t ? TB2 : 0) + 768 + 2 * t), c1 = lds16(tb + TB2 + 770 + 2 * t);
    const uint32_t a2 = lds16(tb + TB2 + 1024 + (t & ~1)), c2 = lds16(tb + TB2 + 1026 + (t & ~1));
    const uint32_t a3 = lds16(tb + TB2 + 1152 + (t & ~1)), c3 = lds16(tb + TB2 + 1154 + (t & ~1));
    if (t < 4) sts128(qb + t * 16, make_uint4(0, 0, 0, 0));
    {
        const uint32_t v1 = w0 & 0xffffu, v2 = lo ? w0 >> 16 : v1, v3 = lo ? w1 & 0xffffu : w0 >> 16, v4 = lo ? w1 >> 16 : w1 & 0xffffu;
        const uint32_t v0 = (t == 0) ? 0u : (t <= 64) ? wm : v1;
        sts128(qb + 64 + 16 * t, make_uint4(v1 | (v0 << 16), v2 | (v1 << 16), v3 | (v2 << 16), v4 | (v3 << 16)));
    }
    {
        const uint32_t m = (t & 1) ? c1 : a1;
        sts128(qb + 64 + 2048 + 16 * t, make_uint4(a1 | (a1 << 16), a1 | (a1 << 16), m | (a1 << 16), c1 | (m << 16)));
    }
    {
        const uint32_t m = (t & 3) == 3 ? c2 : a2, z = (t & 1) ? c2 : a2;
        sts128(qb + 64 + 4096 + 16 * t, make_uint4(m | (a2 << 16), z | (m << 16), z | (z << 16), z | (z << 16)));
    }
    {
        const uint32_t m = (t & 3) == 3 ? c3 : a3, z = (t & 1) ? c3 : a3;
        sts128(qb + 64 + 6144 + 16 * t, make_uint4(m | (a3 << 16), z | (m << 16), z | (z << 16), z | (z << 16)));
    }
}

__device__ __forceinline__ void conv_loadA(uint32_t* a, uint32_t qa) {
#pragma unroll
    for (int s = 0; s < 2; s++) {
        a[4 * s + 0] = lds32(qa + s * 256);
        a[4 * s + 1] = lds32(qa + s * 256 + 64);
        a[4 * s + 2] = lds32(qa + s * 256 - 32);
        a[4 * s + 3] = lds32(qa + s * 256 + 32);
    }
}
template <int G> __device__ __forceinline__ void conv_groups(float (*d)[16], uint32_t (*A)[8], uint32_t qa, uint64_t hd) {
    if constexpr (G < 16) {
        wg_fence();
#pragma unroll
        for (int s = 0; s < 2; s++) {
            const uint32_t* a = &A[G % 3][4 * s];
#pragma unroll
            for (int be = 3; be >= G / 4; be--)
                wgmma_rs_n32<0>(d[be], a[0], a[1], a[2], a[3], hd + (28 + 32 * be - 4 * (2 * G + s)), G + s > 0);
        }
        wg_commit();
        if constexpr (G + 2 < 16) {
            wg_wait<1>();
            conv_loadA(A[(G + 2) % 3], qa + (G + 2) * 512);
        }
        conv_groups<G + 1>(d, A, qa, hd);
    }
}

__global__ void __cluster_dims__(2, 1, 1) __launch_bounds__(384, 1)
fused_kernel(const Params P, const __grid_constant__ CUtensorMap m_w1, const __grid_constant__ CUtensorMap m_g4, const __grid_constant__ CUtensorMap m_u4,
             const __grid_constant__ CUtensorMap m_g3, const __grid_constant__ CUtensorMap m_u3, const __grid_constant__ CUtensorMap m_wd,
             const __grid_constant__ CUtensorMap m_a, const __grid_constant__ CUtensorMap m_out, const __grid_constant__ CUtensorMap m_gs,
             const __grid_constant__ CUtensorMap m_us, const __grid_constant__ CUtensorMap m_t, const __grid_constant__ CUtensorMap m_wm,
             const __grid_constant__ CUtensorMap m_o3, const __grid_constant__ CUtensorMap m_x3,
             const __grid_constant__ CUtensorMap m_xs, const __grid_constant__ CUtensorMap m_st) {
    extern __shared__ __align__(1024) unsigned char smem_raw[];
    const uint32_t sb = (uint32_t)__cvta_generic_to_shared(smem_raw);
    const int tid = (threadIdx.x + 256) % 384, b = blockIdx.x;
    const int wg = __shfl_sync(0xffffffffu, tid >> 7, 0);
    const int warp = __shfl_sync(0xffffffffu, tid >> 5, 0);
    const int lane = tid & 31, t = tid & 127, wp = warp & 3, g = lane >> 2, t4 = lane & 3;
    const uint32_t bars = sb + SM_BAR;
    const uint32_t stg = sb + SM_STG + wg * 32768;
    const int tile = b >> 3, slice = b & 7;
    PROF_DECL;
    PROF_INIT;
    PROF(0);
    PROFG(14);

    auto qslot = [&](int ci) { return sb + SM_Q + ci * Q_STRIDE; };
    const bool mod1 = b < 120, mod2 = b < 80;
    const int third = b / 40;
    {
        uint4 cl = make_uint4(0, 0, 0, 0);
        if (wg == 2 && t < 80) cl = ldcg128(P.c + 8 * t);
        unsigned short kp[2][5];
        uint2 kc[2][2];
#pragma unroll
        for (int r = 0; r < 2; r++) {
            const int ch = 5 * b + ((wg < 2) ? wg + 3 * r : 2), o = ch * 128;
            kp[r][0] = __ldg((const unsigned short*)P.logA + o + t); kp[r][1] = __ldg((const unsigned short*)P.Aim + o + t);
            kp[r][2] = __ldg((const unsigned short*)P.Cre + o + t); kp[r][3] = __ldg((const unsigned short*)P.Cim + o + t);
            kp[r][4] = __ldg((const unsigned short*)P.logdt + ch);
            kc[r][0] = __ldg((const uint2*)(P.Cre + o) + lane); kc[r][1] = __ldg((const uint2*)(P.Cim + o) + lane);
        }
        if (lane == 0) {
            if (warp == 8) {
                mbar_init(bars + 8 * B_XR, 1);
                mbar_expect(bars + 8 * B_XR, 20480);
                tma3d(sb + SM_XROW, &m_x3, 0, 16 * b, 0, bars + 8 * B_XR);
            } else if (warp == 9) {
                mbar_init(bars + 8 * B_X, 1);
                mbar_expect(bars + 8 * B_X, 14336);
                if (mod1) tma2d(sb + SM_W1, &m_w1, 32 * (b - 40 * third), 208 * third, bars + 8 * B_X);
            } else {
#pragma unroll 1
                for (int i = B_WM + warp - (warp > 9 ? 2 : 0); i < B_COUNT; i += 10) {
                    mbar_init(bars + 8 * i, ((i >= B_EMPTY && i < B_RDY) || i == B_TF) ? 2 : (i >= B_RDY && i < B_OE) ? 4 : (i == B_STF) ? 3 : 1);
                    if (i == B_RECV || i == B_RECV + 1) mbar_expect(bars + 8 * i, 28672);
                }
                asm volatile("prefetch.tensormap [%0];" ::"l"((const char*)&m_w1 + 128 * (warp + 1 + (warp > 7 ? 2 : 0))) : "memory");
            }
            asm volatile("fence.mbarrier_init.release.cluster;" ::: "memory");
        }
        if (tid == 256) sts128(sb + SM_RED + 2048, make_uint4(0, 0, 0, 0));
        __syncthreads();
        if (wg == 2) {
            if (t < 88) {
                const uint32_t w[4] = {cl.x, cl.y, cl.z, cl.w};
                uint32_t o[4];
#pragma unroll
                for (int e = 0; e < 4; e++) o[e] = pack_bf(silu_f(bf_lo(w[e])), silu_f(bf_hi(w[e])));
                sts128(sb + SM_RED + 16 * t, make_uint4(o[0], o[1], o[2], o[3]));
                const int i1 = t - 26 * third;
                if (i1 >= 0 && i1 < 35) sts128(sb + SM_RED + 1408 + 16 * i1, (third && i1 < 2) ? make_uint4(0, 0, 0, 0) : make_uint4(o[0], o[1], o[2], o[3]));
            }
            PROF(22);
            mbar_wait(bars + 8 * B_XR, 0);
            PROF(23);
            if (t == 96 && mod2) {
                mbar_expect(bars + 8 * B_WM, 40960);
                tma3d(sb + SM_RING, &m_wm, 2 * D_ + 32 * b, 0, 0, bars + 8 * B_WM);
            }
            __syncwarp();
            {
                const uint32_t xa = sb + SM_XROW + (lane & 15) * 128 + (((lane >> 4) ^ (lane & 7)) << 4);
                const int oc = (lane & 7) + 8 * (lane >> 4);
                const uint32_t dst = sb + SM_RING + XS_OFF + oc * 32 + ((((lane >> 3) ^ (oc >> 2)) & 1) << 4) + wp * 512;
                uint32_t r[10][4];
#pragma unroll
                for (int i = 0; i < 10; i++)
                    asm volatile("ldmatrix.sync.aligned.m8n8.x4.trans.shared.b16 {%0,%1,%2,%3}, [%4];"
                                 : "=r"(r[i][0]), "=r"(r[i][1]), "=r"(r[i][2]), "=r"(r[i][3]) : "r"((xa ^ (wp << 5)) + i * 2048) : "memory");
#pragma unroll
                for (int i = 0; i < 10; i++)
                    asm volatile("stmatrix.sync.aligned.m8n8.x4.shared.b16 [%0], {%1,%2,%3,%4};"
                                 ::"r"(dst + i * 2048), "r"(r[i][0]), "r"(r[i][1]), "r"(r[i][2]), "r"(r[i][3]) : "memory");
                fence_async_smem();
#pragma unroll
                for (int i = 0; i < 10; i++)
                    asm volatile("ldmatrix.sync.aligned.m8n8.x4.shared.b16 {%0,%1,%2,%3}, [%4];"
                                 : "=r"(r[i][0]), "=r"(r[i][1]), "=r"(r[i][2]), "=r"(r[i][3]) : "r"((xa ^ (wp << 5)) + i * 2048) : "memory");
                bar_sync(3, 128);
                if (t == 0) {
                    asm volatile("cp.async.bulk.tensor.3d.global.shared::cta.bulk_group [%0, {%2, %3, %4}], [%1];"
                                 ::"l"(&m_xs), "r"(sb + SM_RING + XS_OFF), "r"(16 * b), "r"(0), "r"(0) : "memory");
                    if (b < 17) bulk_s2g(&g_ctr[C_B2 + 32 * b], sb + SM_RED + 2048, 16);
                }
                __syncwarp();
                PROF(46);
                float sm_[2][4], qa_[2][4], qb_[2][4];
#pragma unroll
                for (int i = 0; i < 4; i++) sm_[0][i] = sm_[1][i] = qa_[0][i] = qa_[1][i] = qb_[0][i] = qb_[1][i] = 0.f;
#pragma unroll
                for (int i = 0; i < 10; i++) {
                    mma16816(sm_[i & 1], r[i][0], r[i][1], r[i][2], r[i][3], 0x3f803f80u, 0x3f803f80u);
                    mma16816(qa_[i & 1], r[i][0], r[i][1], r[i][2], r[i][3], r[i][0], r[i][2]);
                    mma16816(qb_[i & 1], r[i][0], r[i][1], r[i][2], r[i][3], r[i][1], r[i][3]);
                }
                if (t4 == (g >> 1)) {
                    const uint32_t ma = sb + SM_MISC + (wp * 32 + g) * 4;
                    sts32(ma, __float_as_uint(sm_[0][0] + sm_[1][0])); sts32(ma + 32, __float_as_uint(sm_[0][2] + sm_[1][2]));
                    sts32(ma + 64, __float_as_uint((g & 1) ? qa_[0][1] + qa_[1][1] : qa_[0][0] + qa_[1][0]));
                    sts32(ma + 96, __float_as_uint((g & 1) ? qb_[0][3] + qb_[1][3] : qb_[0][2] + qb_[1][2]));
                }
                bar_sync(3, 128);
            }
            if (wp < 2) {
                PROF(24);
                if (wp == 1) {
                    float ss = 0.f;
#pragma unroll
                    for (int w = 0; w < 4; w++) ss += __uint_as_float(lds32(sb + SM_MISC + (w * 32 + lane) * 4));
                    const float qq = __shfl_down_sync(0xffffffffu, ss, 16);
                    const float mu = ss * (1.0f / D_);
                    const float rs = rsqrtf(fmaxf(qq * (1.0f / D_) - mu * mu, 0.f) + 1e-5f);
                    if (lane < 16) { sts32(sb + SM_MISC + 512 + lane * 8, __float_as_uint(rs)); sts32(sb + SM_MISC + 516 + lane * 8, __float_as_uint(-mu * rs)); }
                    fence_async_smem();
                    __syncwarp();
                    if (lane == 0) {
                        bulk_s2g(g_stats1 + 16 * b, sb + SM_MISC + 512, 128);
                        asm volatile("cp.async.bulk.commit_group;" ::: "memory");
                    }
                }
                __syncwarp();
            }
            __syncwarp();
            if (mod1) {
                mbar_wait(bars + 8 * B_X, 0);
                PROF(44);
                float md[16];
                row_mma<14>(md, mk64((((sb + SM_RED + 1408) & 0x3FFFF) >> 4) | (1 << 16), 0), 2,
                            mk64((((sb + SM_W1) & 0x3FFFF) >> 4) | (128 << 16), 0x80000020), 14);
                if (t < 4) {
#pragma unroll
                    for (int j = 0; j < 4; j++) { sts32(sb + SM_RED + 2176 + (8 * j + 2 * t) * 4, __float_as_uint(md[4 * j])); sts32(sb + SM_RED + 2180 + (8 * j + 2 * t) * 4, __float_as_uint(md[4 * j + 1])); }
                    fence_async_smem();
                }
                __syncwarp();
                if (t == 0) bulk_s2g(g_sc + third * (2 * D_) + 32 * (b - 40 * third), sb + SM_RED + 2176, 128);
                PROF(45);
            }
            if (t == 32) {
                asm volatile("cp.async.bulk.wait_group 0;" ::: "memory");
                mbar_arrive(bars + 8 * B_XS);
            } else if (t == 0) {
                asm volatile("cp.async.bulk.commit_group;" ::: "memory");
                PROF(9);
                asm volatile("cp.async.bulk.wait_group 0;" ::: "memory");
                mbar_wait(bars + 8 * B_XS, 0);
                PROF(10);
                asm volatile("red.add.relaxed.gpu.global.u32 [%0], 1;" ::"l"(&g_ctr[C_B1]) : "memory");
                PROF(11);
            }
            __syncwarp();
            if (mod2) {
                mbar_wait(bars + 8 * B_WM, 0);
                float md[16];
                row_mma<8>(md, mk64((((sb + SM_RED) & 0x3FFFF) >> 4) | (1 << 16), 0), 2, mk64((((sb + SM_RING) & 0x3FFFF) >> 4) | (128 << 16), 0x80000020), 40);
                bar_sync(3, 128);
                if (t < 4) {
                    const int vec = b / 20, d0 = 32 * (b - 20 * vec) + 2 * t;
#pragma unroll
                    for (int j = 0; j < 4; j++) {
                        uint32_t pv = pack_bf(md[4 * j], md[4 * j + 1]);
                        if (vec == 2) pv = pack_bf(1.0f + bf_lo(pv), 1.0f + bf_hi(pv));
                        if (vec == 3) *(uint32_t*)(g_gb + d0 + 8 * j) = pv;
                        if (!(vec & 1)) *(float2*)((vec ? g_cb1 : g_ga) + d0 + 8 * j) = make_float2(bf_lo(pv), bf_hi(pv));
                        if (vec == 1 || vec == 2) *(uint32_t*)(g_csb + ((d0 >> 3) + j) * 16 + (2 - vec) * 8 + 2 * t) = pv;
                    }
                }
                __syncwarp();
            }
            if (t == 0) grid_arrive_red(&g_ctr[C_MOD]);
            if (t == 32) {
                if (b < 108) {
                    mbar_expect(bars + 8 * B_W, 40960);
                    tma3d(sb + SM_RING, b < 54 ? &m_gs : &m_us, 32 * (b % 54), 0, 0, bars + 8 * B_W);
                }
                l2_prefetch((const char*)P.wd + b * 17280, 17280);
            }
            __syncwarp();
            PROF(2);
        }
        KHead kh = kgen_head(bf_lo(kp[0][4]), bf_lo(kp[0][0]), bf_lo(kp[0][1]), bf_lo(kp[0][2]), bf_lo(kp[0][3]), cmax2(kc[0][0], kc[0][1]));
        const uint64_t hd = mk64(((stg & 0x3FFFF) >> 4) | ((H1_OFF >> 4) << 16), 0x00000008);
        const int tt = g + 8 * (wp & 1), pl = wp >> 1;
        const int ea = 32 * wp + (lane & 15), eh = lane >> 4;
        const int nstep = (wg < 2) ? 4 : 2;
        float mv = 0.f;
#pragma unroll 1
        for (int step = 0; step < nstep; step++) {
            const bool isk = step < nstep / 2;
            const int r = (wg < 2) ? (step & 1) : 0;
            const int ci = wg + 3 * r;
            if (isk) {
                PROF(26 + 3 * r);
                kgen_body(kh, stg, t);
                const float osc = kh.osc;
                fence_async_smem();
                bar_sync(1 + wg, 128);
                PROF(27 + 3 * r);
                float kd[8];
                uint64_t sd = mk64(((stg & 0x3FFFF) >> 4) | (1 << 16), 0x40000040);
                asm volatile("" : "+l"(sd));
                wg_fence();
#pragma unroll
                for (int k = 0; k < 16; k++) {
                    const uint32_t o = (k >> 2) * 512 + (k & 3) * 2;
                    wgmma_ss_n16_f16<0, 0>(kd, sd + o, sd + (o + 384), k > 0);
                }
                wg_commit();
                if (step == 0 && wg < 2) kh = kgen_head(bf_lo(kp[1][4]), bf_lo(kp[1][0]), bf_lo(kp[1][1]), bf_lo(kp[1][2]), bf_lo(kp[1][3]), cmax2(kc[1][0], kc[1][1]));
                wg_wait<0>();
                fence_regs<8>(kd);
                PROF(28 + 3 * r);
                if (r == 1) mbar_wait(bars + 8 * B_XS, 0);
                kgen_tail(kd, osc, stg, qslot(ci), wg, t);
                PROF(1);
                continue;
            }
            const int ch = 5 * b + ci;
            const float dsk = ldbf(P.Dskip + ch);
            if (r == 0) {
                if (tid == 0) {
                    grid_wait(&g_ctr[C_B1], NCTA);
                    mbar_arrive(bars + 8 * B_G1);
                    fence_async_gmem();
                    mbar_expect(bars + 8 * B_ST, 16384 + 20480);
                    tma2d(sb + SM_RING + 3 * 16384, &m_st, 0, 0, bars + 8 * B_ST);
                    bulk_g2s(sb + SM_XT, g_xT + (size_t)5 * b * L_, 20480, bars + 8 * B_ST);
                }
                mbar_wait(bars + 8 * B_G1, 0);
                PROF(4);
                mv = ldcgf(g_sc + min(lane >> 2, 2) * (2 * D_) + (lane & 1) * D_ + 5 * b + ((wg < 2) ? wg + 3 * ((lane >> 1) & 1) : 2));
                if (warp == 8) {
                    if (lane == 0) {
                        grid_wait(&g_ctr[C_MOD], NCTA);
                        fence_async_gmem();
                        mbar_expect(bars + 8 * B_CS, 2560);
                        bulk_g2s(sb + SM_RING + CS_OFF, g_csb, 2560, bars + 8 * B_CS);
                    }
                    __syncwarp();
                    if (lane < 10) sts32(sb + SM_MISC + 704 + lane * 4, __float_as_uint(ldcgf(lane < 5 ? g_ga + 5 * b + lane : g_cb1 + 5 * b + lane - 5)));
                    __syncwarp();
                    if (lane == 0) mbar_arrive(bars + 8 * B_MOD);
                }
                mv = bfr(mv + __shfl_down_sync(0xffffffffu, mv, 4) + __shfl_down_sync(0xffffffffu, mv, 8));
                if (lane & 1) mv = bfr(1.0f + mv);
                mbar_wait(bars + 8 * B_ST, 0);
            }
            const float sa = __shfl_sync(0xffffffffu, mv, 2 * r), ca1 = __shfl_sync(0xffffffffu, mv, 2 * r + 1);
            uint32_t xv[8], hv[8];
            {
                if (t < 28) { sts128(stg + t * 16, make_uint4(0, 0, 0, 0)); sts128(stg + H1_OFF + t * 16, make_uint4(0, 0, 0, 0)); }
                const uint32_t xa = sb + SM_XT + ci * XT_STRIDE + ea * 32 + eh * 16;
                const uint4 x0 = lds128(xa), x1 = lds128(xa + 512);
                xv[0] = x0.x; xv[1] = x0.y; xv[2] = x0.z; xv[3] = x0.w; xv[4] = x1.x; xv[5] = x1.y; xv[6] = x1.z; xv[7] = x1.w;
                const uint32_t sta = sb + SM_RING + 3 * 16384 + ea * 128 + (((eh * 4) ^ (lane & 7)) << 4);
#pragma unroll
                for (int i = 0; i < 8; i++) {
                    const uint4 v = lds128((sta ^ ((i & 3) << 4)) + (i >> 2) * 2048);
                    const float n0 = fmaf(bf_lo(xv[i]), __uint_as_float(v.x), __uint_as_float(v.y)), n1 = fmaf(bf_hi(xv[i]), __uint_as_float(v.z), __uint_as_float(v.w));
                    hv[i] = pack_bf(fmaf(n0, ca1, sa), fmaf(n1, ca1, sa));
                }
                const uint32_t ha = stg + eh * H1_OFF + 448 + ea * 16;
                sts128(ha, make_uint4(hv[0], hv[1], hv[2], hv[3]));
                sts128(ha + 256, make_uint4(hv[4], hv[5], hv[6], hv[7]));
            }
            PROF(16 + 5 * r);
            const uint32_t qa = qslot(ci) + 4 * (16 + tt + 32 * pl - 2 * t4);
            fence_async_smem();
            bar_sync(1 + wg, 128);
            uint32_t A[3][8];
            conv_loadA(A[0], qa);
            conv_loadA(A[1], qa + 512);
            if (step == nstep - 1 && t == 0) mbar_arrive(bars + 8 * B_STF);
            PROF(17 + 5 * r);
            float dd[4][16];
            uint64_t hu = hd;
            asm volatile("" : "+l"(hu));
            conv_groups<0>(dd, A, qa, hu);
            wg_wait<0>();
            float* d = &dd[0][0];
            fence_regs<64>(d);
            PROF(18 + 5 * r);
            const uint32_t xw = stg + XP_OFF + pl * XP_PLANE + (2 * t4) * 80 + tt * 4;
            const int src = (lane & ~3) | ((t4 + 3) & 3);
#pragma unroll
            for (int j = 0; j < 16; j++) {
                const float snd = (t4 == 3) ? (j > 0 ? d[4 * j - 1] : 0.f) : d[4 * j + 3];
                const float rcv = __shfl_sync(0xffffffffu, snd, src);
                sts32(xw + j * 640, __float_as_uint(d[4 * j] + rcv));
                sts32(xw + j * 640 + 80, __float_as_uint(d[4 * j + 1] + d[4 * j + 2]));
            }
            bar_sync(1 + wg, 128);
            mbar_wait(bars + 8 * B_MOD, 0);
            PROF(19 + 5 * r);
            const float ga = __uint_as_float(lds32(sb + SM_MISC + 704 + ci * 4)), cb1 = __uint_as_float(lds32(sb + SM_MISC + 724 + ci * 4));
#pragma unroll
            for (int it = 0; it < 2; it++) {
                const int a = ea + 16 * it;
                uint32_t o2[4], o2p[4];
#pragma unroll
                for (int i = 0; i < 2; i++) {
                    const uint4 y0 = lds128(stg + XP_OFF + a * 80 + eh * 32 + i * 16);
                    uint4 y1 = make_uint4(0, 0, 0, 0);
                    if (a >= 2) y1 = lds128(stg + XP_OFF + XP_PLANE + (a - 2) * 80 + eh * 32 + i * 16);
                    const float y[4] = {__uint_as_float(y0.x) + __uint_as_float(y1.x), __uint_as_float(y0.y) + __uint_as_float(y1.y),
                                        __uint_as_float(y0.z) + __uint_as_float(y1.z), __uint_as_float(y0.w) + __uint_as_float(y1.w)};
#pragma unroll
                    for (int e = 0; e < 2; e++) {
                        const int k = 4 * it + 2 * i + e;
                        const float v0 = fmaf(ga, fmaf(bf_lo(hv[k]), dsk, y[2 * e]), bf_lo(xv[k]));
                        const float v1 = fmaf(ga, fmaf(bf_hi(hv[k]), dsk, y[2 * e + 1]), bf_hi(xv[k]));
                        o2[2 * i + e] = pack_bf(v0, v1);
                        o2p[2 * i + e] = pack_bf(bf_lo(o2[2 * i + e]) * cb1, bf_hi(o2[2 * i + e]) * cb1);
                    }
                }
                sts128(qslot(ci) + a * 32 + eh * 16, make_uint4(o2p[0], o2p[1], o2p[2], o2p[3]));
                sts128(qslot(ci) + 4096 + a * 32 + eh * 16, make_uint4(o2[0], o2[1], o2[2], o2[3]));
            }
            fence_async_smem();
            __syncwarp();
            if (lane == 0) {
                bulk_s2g(g_x2pT + (size_t)ch * L_ + 512 * wp, qslot(ci) + 1024 * wp, 1024);
                bulk_s2g(g_x2T + (size_t)ch * L_ + 512 * wp, qslot(ci) + 4096 + 1024 * wp, 1024);
                asm volatile("cp.async.bulk.commit_group;" ::: "memory");
            }
            PROF(20 + 5 * r);
        }
    }
    PROF(5);
    if (wg == 2) {
        if (b < 108) {
            mbar_wait(bars + 8 * B_CS, 0);
            mbar_wait(bars + 8 * B_W, 0);
            float sd_[16];
            const uint64_t wb_ = mk64((((sb + SM_RING) & 0x3FFFF) >> 4) | (128 << 16), 0x80000020);
            row_mma<8>(sd_, mk64((((sb + SM_RING + CS_OFF) & 0x3FFFF) >> 4) | (2 << 16), 0), 4, wb_, 40);
            if (t < 8) {
                const float sc = b < 54 ? 1.0f : 0.5f;
#pragma unroll
                for (int j = 0; j < 4; j++) {
                    sts32(sb + SM_MISC + (8 * j + 2 * t4) * 8 + g * 4, __float_as_uint(sd_[4 * j] * sc));
                    sts32(sb + SM_MISC + (8 * j + 2 * t4) * 8 + 8 + g * 4, __float_as_uint(sd_[4 * j + 1] * sc));
                }
                fence_async_smem();
            }
            bar_sync(3, 128);
            if (t == 0) bulk_s2g(g_tab + (b < 54 ? 0 : FP_) + 32 * (b % 54), sb + SM_MISC, 256);
        } else if (b >= 126) {
            if (t < 32) { sts128(sb + SM_MISC + 16 * t, make_uint4(0, 0, 0, 0)); fence_async_smem(); }
            __syncwarp();
            if (t == 0) bulk_s2g(g_tab + (b - 126) * FP_ + F_, sb + SM_MISC, 512);
        }
        if (tid == 256) {
            mbar_wait(bars + 8 * B_CS, 0);
#pragma unroll 1
            for (int s = 0; s < 4; s++) {
                if (s == 3) mbar_wait(bars + 8 * B_STF, 0);
                mbar_expect(bars + 8 * (B_FULL + s), 16384);
                tma3d(sb + SM_RING + s * 16384, &m_g4, 0, s * 32, slice * 7, bars + 8 * (B_FULL + s));
                tma3d(sb + SM_RING + s * 16384 + 8192, &m_u4, 0, s * 32, slice * 7, bars + 8 * (B_FULL + s));
            }
        }
    }
    PROF(6);
    if (lane == 0) asm volatile("cp.async.bulk.commit_group;\ncp.async.bulk.wait_group 0;" ::: "memory");
    __syncthreads();
    PROF(3);
    if (tid == 256) {
        asm volatile("red.add.relaxed.gpu.global.u32 [%0], 1;" ::"l"(&g_ctr[C_B2]) : "memory");
        grid_wait(&g_ctr[C_B2], NCTA);
        fence_async_gmem();
#pragma unroll 1
        for (int c = 0; c < 3; c++) {
            mbar_expect(bars + 8 * (B_A + c), 16384);
            tma2d_pair(sb + (b & 1) * A_HALF + c * 8192, &m_a, tile * 128 + (b & 1) * 64, c * 64, bars + 8 * (B_A + c));
        }
        mbar_expect(bars + 8 * B_T, 20480);
        tma2d(sb + TIN_OFF, &m_t, tile * 128 + slice * 16, 0, bars + 8 * B_T);
        mbar_arrive(bars + 8 * B_G1);
        if (b == 0) { g_ctr[C_B1] = 0; g_ctr[C_MOD] = 0; }
    }
    PROF(7);

    if (wg == 2) {
        if (wp != 0) {
            const int tok0 = tile * 128 + slice * 16;
            mbar_wait(bars + 8 * B_G1, 1);
            if (wp == 3) {
                float acc = 0.f;
                if (lane < 28) acc += ldca64f((const char*)(g_tab + (lane >= 14 ? FP_ : 0) + slice * 224) + (lane % 14) * 128).x;
                if (lane < 5) acc += ldca64f((const char*)(g_gb + (slice & 1) * 320) + lane * 128).x;
                if (acc == 1.2345e-30f) g_ga[0] = acc;
            }
            mbar_wait(bars + 8 * B_T, 0);
            PROFT(33);
            const int lc = lane & 15;
            const uint32_t src = sb + TIN_OFF + (wp - 1) * 512 + lc * 32 + (((lane >> 4) ^ ((lc >> 2) & 1)) << 4);
            const uint32_t dst = sb + A_HALF + TIN_OFF + ((lane & 7) + 8 * (lane >> 4)) * 128 + ((((lane >> 3) & 1) ^ (lane & 7)) << 4);
            uint32_t r[14][4];
#pragma unroll
            for (int u = 0; u < 14; u++) {
                if (u < 13 || wp == 1)
                    asm volatile("ldmatrix.sync.aligned.m8n8.x4.trans.shared.b16 {%0,%1,%2,%3}, [%4];"
                                 : "=r"(r[u][0]), "=r"(r[u][1]), "=r"(r[u][2]), "=r"(r[u][3]) : "r"(src + u * 1536) : "memory");
                else r[u][0] = r[u][1] = r[u][2] = r[u][3] = 0;
            }
#pragma unroll
            for (int u = 0; u < 14; u++)
                if (u < 13 || wp == 1) {
                    const int cb = wp - 1 + 3 * u;
                    asm volatile("stmatrix.sync.aligned.m8n8.x4.shared.b16 [%0], {%1,%2,%3,%4};"
                                 ::"r"((dst ^ ((cb & 3) << 5)) + (cb >> 2) * 2048), "r"(r[u][0]), "r"(r[u][1]), "r"(r[u][2]), "r"(r[u][3]) : "memory");
                }
            fence_async_smem();
            bar_sync(4, 96);
            PROFT(34);
            if (t == 64) {
                asm volatile("cp.async.bulk.tensor.3d.global.shared::cta.bulk_group [%0, {%2, %3, %4}], [%1];"
                             ::"l"(&m_o3), "r"(sb + A_HALF + TIN_OFF), "r"(0), "r"(tok0), "r"(0) : "memory");
                asm volatile("cp.async.bulk.commit_group;" ::: "memory");
                asm volatile("cp.async.bulk.wait_group.read 0;" ::: "memory");
#pragma unroll
                for (int c = 0; c < 2; c++)
                    asm volatile("{ .reg .b32 ra; mapa.shared::cluster.u32 ra, %0, %1; mbarrier.arrive.relaxed.cluster.shared::cluster.b64 _, [ra]; }"
                                 ::"r"(bars + 8 * B_TF), "r"(c) : "memory");
            }
            __syncwarp();
            float s0 = 0.f, q0 = 0.f, s1 = 0.f, q1 = 0.f;
#pragma unroll
            for (int u = 0; u < 14; u++) {
                const float a0 = bf_lo(r[u][0]), a1 = bf_hi(r[u][0]), a2 = bf_lo(r[u][1]), a3 = bf_hi(r[u][1]);
                const float c0 = bf_lo(r[u][2]), c1 = bf_hi(r[u][2]), c2 = bf_lo(r[u][3]), c3 = bf_hi(r[u][3]);
                s0 += (a0 + a1) + (a2 + a3); s1 += (c0 + c1) + (c2 + c3);
                q0 = fmaf(a0, a0, fmaf(a1, a1, fmaf(a2, a2, fmaf(a3, a3, q0))));
                q1 = fmaf(c0, c0, fmaf(c1, c1, fmaf(c2, c2, fmaf(c3, c3, q1))));
            }
#pragma unroll
            for (int m = 1; m < 4; m <<= 1) {
                s0 += __shfl_xor_sync(0xffffffffu, s0, m); q0 += __shfl_xor_sync(0xffffffffu, q0, m);
                s1 += __shfl_xor_sync(0xffffffffu, s1, m); q1 += __shfl_xor_sync(0xffffffffu, q1, m);
            }
            if (t4 == 0) {
                const uint32_t ma = sb + SM_MISC + ((wp - 1) * 32 + g) * 4;
                sts32(ma, __float_as_uint(s0)); sts32(ma + 32, __float_as_uint(s1)); sts32(ma + 64, __float_as_uint(q0)); sts32(ma + 96, __float_as_uint(q1));
            }
            if (t == 64) asm volatile("cp.async.bulk.wait_group 0;" ::: "memory");
            bar_sync(4, 96);
            if (wp == 1) {
                if (lane < 16) {
                    float ss = 0.f, qq = 0.f;
#pragma unroll
                    for (int w = 0; w < 3; w++) { ss += __uint_as_float(lds32(sb + SM_MISC + (w * 32 + lane) * 4)); qq += __uint_as_float(lds32(sb + SM_MISC + (w * 32 + 16 + lane) * 4)); }
                    const float mu = ss * (1.0f / D_);
                    const float var = fmaxf(qq * (1.0f / D_) - mu * mu, 0.f);
                    const float rs = rsqrtf(var + 1e-5f);
                    sts32(sb + SM_MISC + 512 + lane * 8, __float_as_uint(rs)); sts32(sb + SM_MISC + 516 + lane * 8, __float_as_uint(-mu * rs));
                    fence_async_smem();
                }
                __syncwarp();
                PROFT(36);
                if (lane == 0) {
                    bulk_s2g(g_stats2 + tok0, sb + SM_MISC + 512, 128);
                    asm volatile("cp.async.bulk.commit_group;\ncp.async.bulk.wait_group 0;" ::: "memory");
                    asm volatile("red.add.relaxed.gpu.global.u32 [%0], 1;" ::"l"(&g_ctr[C_TILE + 32 * tile]) : "memory");
                    unsigned int v;
                    int it = 0;
#pragma unroll 1
                    do {
                        asm volatile("ld.relaxed.gpu.global.u32 %0, [%1];" : "=r"(v) : "l"(&g_ctr[C_TILE + 32 * tile]) : "memory");
                    } while (v < 8 && ++it < SPIN_LIMIT);
                    fence_async_gmem();
                    mbar_expect(bars + 8 * B_E1, 1024);
                    bulk_g2s(sb + SM_ST2, g_stats2 + tile * 128, 1024, bars + 8 * B_E1);
                }
                __syncwarp();
            }
        }
        asm volatile("setmaxnreg.dec.sync.aligned.u32 40;");
        if (tid == 256) {
            const uint32_t ring = sb + SM_RING;
#pragma unroll 1
            for (int it = 4; it < 20; it++) {
                const int s = it & 3;
                const uint32_t fb = bars + 8 * (B_FULL + s);
                if (it != 12 && !(it & 1)) {
                    const int c = (it >> 1) + (it < 12);
                    if (c == 7) mbar_wait(bars + 8 * B_TF, 0);
                    mbar_expect(bars + 8 * (B_A + c), 16384);
                    tma2d_pair(sb + (b & 1) * A_HALF + c * 8192, &m_a, tile * 128 + (b & 1) * 64, c * 64, bars + 8 * (B_A + c));
                }
                if (it < 8) tma2d(sb + TIN_OFF + (it - 3) * 4096, &m_t, tile * 128 + slice * 16, (it - 3) * 128, bars + 8 * B_T);
                mbar_wait(bars + 8 * (B_EMPTY + s), ((it >> 2) & 1) ^ 1);
                mbar_expect(fb, 16384);
                tma3d(ring + s * 16384, &m_g4, 0, it * 32, slice * 7, fb);
                tma3d(ring + s * 16384 + 8192, &m_u4, 0, it * 32, slice * 7, fb);
            }
            {
                int s = 0, n = 0;
#pragma unroll 1
                for (int k = 0; k < 20; k++) {
                    const uint32_t fb = bars + 8 * (B_FULL + s);
                    if (s < 4) mbar_wait(bars + 8 * (B_EMPTY + s), n & 1);
                    else if (n > 0) mbar_wait(bars + 8 * (B_EMPTY + s), (n & 1) ^ 1);
                    mbar_expect(fb, 12288);
                    tma3d(ring + s * 12288, &m_g3, 0, k * 32, slice * 7 + 4, fb);
                    tma3d(ring + s * 12288 + 6144, &m_u3, 0, k * 32, slice * 7 + 4, fb);
                    if (++s == 5) { s = 0; n++; }
                }
            }
            mbar_wait(bars + 8 * B_EMPTY, 0);
#pragma unroll 1
            for (int j = 0; j < 20; j++) {
                const int s = j & 7;
                const uint32_t fb = bars + 8 * (B_FULL + s);
                if (j < 4) mbar_wait(bars + 8 * (B_EMPTY + j + 1), j == 3);
                else if (j < 8) mbar_wait(bars + 8 * (B_DEAD + ((s >> 1) & 1)), 0);
                else mbar_wait(bars + 8 * (B_EMPTY + s), ((j >> 4) & 1) ^ (s < 4));
                mbar_expect(fb, 14336);
                tma2d(s < 4 ? ring + s * 16384 : sb + ((s >> 1) & 1) * A_HALF + XSLOT_OFF + (s & 1) * 16384, &m_wd,
                      (slice & 1) * 320 + (j < 16 ? 2 * (j >> 3) + ((j >> 1) & 1) : 4) * 64,
                      (slice ^ ((j >> (j < 16 ? 2 : 1)) & 1)) * 224 + (j & 1) * 112, fb);
            }
        } else if (wp >= 2 && lane == 0) {
            const int w = wp - 2;
#pragma unroll 1
            for (int c = 0; c < 5; c++) {
                mbar_wait(bars + 8 * (B_OF + 2 * w + (c & 1)), (c >> 1) & 1);
                if (c == 0) fence_async_gmem();
                tma_red2d(&m_out, (slice & 1) * 320 + c * 64, tile * 128 + w * 64, sb + w * A_HALF + OST_OFF + (c & 1) * 8192);
                asm volatile("cp.async.bulk.commit_group;" ::: "memory");
                asm volatile("cp.async.bulk.wait_group.read 0;" ::: "memory");
                mbar_arrive(bars + 8 * (B_OE + 2 * w + (c & 1)));
            }
            asm volatile("cp.async.bulk.wait_group 0;" ::: "memory");
        }
    } else {
        const uint64_t ad = mk64((((sb + wg * A_HALF) & 0x3FFFF) >> 4) | (64 << 16), 0x40000040);
        const uint64_t bd1 = mk64((((sb + SM_RING) & 0x3FFFF) >> 4) | (128 << 16), 0x80000020);
        const uint64_t bd2 = mk64(((sb & 0x3FFFF) >> 4) | (64 << 16), 0x40000040);
        const uint32_t fb = bars + 8 * B_FULL, eb = bars + 8 * B_EMPTY, ab = bars + 8 * B_A;
        uint32_t hh[112];
        const float2* tab = g_tab + slice * 224 + 2 * t4;
        float rs0, nm0, rs1, nm1;
        if (wg == 1) asm volatile("bar.arrive 8, 256;" ::: "memory");
        {
            float d[128];
            const bool leader = (t == 0);
#pragma unroll 1
            for (int n = 0; n < 5; n++) {
                const uint64_t an = ad + n * 1024;
                uint64_t bu = bd1;
                asm volatile("" : "+l"(bu));
#pragma unroll
                for (int s = 0; s < 4; s++) {
                    if (!(s & 1)) mbar_wait(ab + 16 * n + 4 * s, 0);
                    mbar_wait(fb + s * 8, n & 1);
                    wg_fence();
#pragma unroll
                    for (int j = 0; j < 2; j++)
                        wgmma_ss_n256<1, 1>(d, an + (s * 2 + j) * 128, bu + (s * 1024 + j * 64), (s + j > 0) || n > 0);
                    wg_commit();
                    wg_wait<1>();
                    if (leader && (s > 0 || n > 0)) mbar_arrive(eb + ((s + 3) & 3) * 8);
                }
                PROF(32 + n);
            }
            wg_wait<0>();
            fence_regs<128>(d);
            if (t == 0) mbar_arrive(eb + 3 * 8);
            PROF(8);
            mbar_wait(bars + 8 * B_E1, 0);
            asm volatile("setmaxnreg.inc.sync.aligned.u32 232;");
            {
                const uint32_t sa_ = sb + SM_ST2 + (wg * 64 + wp * 16 + g) * 8;
                rs0 = __uint_as_float(lds32(sa_)); nm0 = __uint_as_float(lds32(sa_ + 4)); rs1 = __uint_as_float(lds32(sa_ + 64)); nm1 = __uint_as_float(lds32(sa_ + 68));
            }
#define GEGLU(gv, uv, rs, nm, g1, g2, u1, u2) ({ const float g_ = fmaf((gv), (rs), fmaf((nm), (g1), (g2))); \
                                    const float u_ = fmaf((uv), 0.5f * (rs), fmaf((nm), (u1), (u2))); \
                                    const float z_ = g_ * fmaf(g_ * g_, 0.035677408136300125f, 0.7978845608028654f); \
                                    fmaf(g_, tanh_fast(z_), g_) * u_; })
#pragma unroll
            for (int j = 0; j < 16; j++) {
                const float4 G = ldca128f(tab + 8 * j), U = ldca128f(tab + FP_ + 8 * j);
                hh[2 * j] = pack_bf(GEGLU(d[4 * j], d[64 + 4 * j], rs0, nm0, G.x, G.y, U.x, U.y), GEGLU(d[4 * j + 1], d[64 + 4 * j + 1], rs0, nm0, G.z, G.w, U.z, U.w));
                hh[2 * j + 1] = pack_bf(GEGLU(d[4 * j + 2], d[64 + 4 * j + 2], rs1, nm1, G.x, G.y, U.x, U.y), GEGLU(d[4 * j + 3], d[64 + 4 * j + 3], rs1, nm1, G.z, G.w, U.z, U.w));
            }
        }
        PROF(9);
        uint32_t rdst, rbar, rrdy;
        asm("mapa.shared::cluster.u32 %0, %1, %2;" : "=r"(rdst) : "r"(sb + wg * A_HALF + RECV_OFF + t * 16), "r"((slice & 1) ^ 1));
        asm("mapa.shared::cluster.u32 %0, %1, %2;" : "=r"(rbar) : "r"(bars + 8 * (B_RECV + wg)), "r"((slice & 1) ^ 1));
        asm("mapa.shared::cluster.u32 %0, %1, %2;" : "=r"(rrdy) : "r"(bars + 8 * (B_RDY + wg)), "r"((slice & 1) ^ 1));
        auto send = [&](int i) {
            asm volatile("st.async.weak.shared::cluster.mbarrier::complete_tx::bytes.v4.b32 [%0], {%1,%2,%3,%4}, [%5];"
                         ::"r"(rdst + i * 2048), "r"(hh[4 * i]), "r"(hh[4 * i + 1]), "r"(hh[4 * i + 2]), "r"(hh[4 * i + 3]), "r"(rbar) : "memory");
        };
        {
            float e[96];
            const bool leader = (t == 0), lane0 = (lane == 0);
#pragma unroll 1
            for (int n = 0; n < 4; n++) {
                const uint64_t an = ad + n * 1280;
                uint64_t bu = bd1;
                asm volatile("" : "+l"(bu));
#pragma unroll
                for (int s = 0; s < 5; s++) {
                    mbar_wait(fb + s * 8, (n & 1) ^ (s < 4));
                    wg_fence();
#pragma unroll
                    for (int j = 0; j < 2; j++)
                        wgmma_ss_n192<1, 1>(e, an + (s * 2 + j) * 128, bu + (s * 768 + j * 64), (s + j > 0) || n > 0);
                    wg_commit();
                    wg_wait<1>();
                    if (leader && (s > 0 || n > 0)) mbar_arrive(eb + ((s + 4) % 5) * 8);
                    if (s == 3 && n == 1 && lane0)
                        asm volatile("mbarrier.arrive.relaxed.cluster.shared::cluster.b64 _, [%0];" ::"r"(rrdy) : "memory");
                    if (s > 0 && n >= 2) {
                        if (s == 1 && n == 2) mbar_wait(bars + 8 * (B_RDY + wg), 0);
                        if (n == 2) send(s - 1); else send(3 + s);
                    }
                }
                PROF(40 + n);
            }
            wg_wait<0>();
            fence_regs<96>(e);
            if (t == 0) mbar_arrive(eb + 4 * 8);
            if (lane == 0) mbar_arrive(bars + 8 * (B_DEAD + wg));
            PROF(10);
#pragma unroll
            for (int j = 0; j < 12; j++) {
                const float4 G = ldca128f(tab + 128 + 8 * j), U = ldca128f(tab + FP_ + 128 + 8 * j);
                hh[32 + 2 * j] = pack_bf(GEGLU(e[4 * j], e[48 + 4 * j], rs0, nm0, G.x, G.y, U.x, U.y), GEGLU(e[4 * j + 1], e[48 + 4 * j + 1], rs0, nm0, G.z, G.w, U.z, U.w));
                hh[32 + 2 * j + 1] = pack_bf(GEGLU(e[4 * j + 2], e[48 + 4 * j + 2], rs1, nm1, G.x, G.y, U.x, U.y), GEGLU(e[4 * j + 3], e[48 + 4 * j + 3], rs1, nm1, G.z, G.w, U.z, U.w));
                if (j & 1) send(8 + (j >> 1));
            }
#undef GEGLU
        }
        PROF(11);
        float o[2][32];
        const uint32_t ost_st = sb + wg * A_HALF + OST_OFF + wp * 2048 + (lane & 15) * 128 + (((lane >> 4) ^ (lane & 7)) << 4);
        const uint32_t* gbp = (const uint32_t*)(g_gb + (slice & 1) * 320 + 2 * t4);
        uint32_t gbv[8];
        auto load_gb = [&](int c) {
#pragma unroll
            for (int i = 0; i < 8; i++) asm volatile("ld.global.ca.b32 %0, [%1];" : "=r"(gbv[i]) : "l"(gbp + c * 32 + i * 4) : "memory");
        };
        auto epilogue = [&](float* acc, int c) {
            if (c == 2) PROF(60);
            fence_regs<32>(acc);
            if (c >= 2) mbar_wait(bars + 8 * (B_OE + 2 * wg + (c & 1)), (c >> 2) & 1);
#pragma unroll
            for (int jj = 0; jj < 4; jj++) {
                const float* a = acc + 8 * jj;
                const uint32_t r0 = hmul_bf(pack_bf(a[0], a[1]), gbv[2 * jj]), r1 = hmul_bf(pack_bf(a[2], a[3]), gbv[2 * jj]);
                const uint32_t r2 = hmul_bf(pack_bf(a[4], a[5]), gbv[2 * jj + 1]), r3 = hmul_bf(pack_bf(a[6], a[7]), gbv[2 * jj + 1]);
                asm volatile("stmatrix.sync.aligned.m8n8.x4.shared.b16 [%0], {%1,%2,%3,%4};"
                             ::"r"((ost_st ^ (jj << 5)) + (c & 1) * 8192), "r"(r0), "r"(r1), "r"(r2), "r"(r3) : "memory");
            }
            if (c == 2) PROF(61);
            fence_async_smem();
            __syncwarp();
            if (lane == 0) mbar_arrive(bars + 8 * (B_OF + 2 * wg + (c & 1)));
        };
        auto unit = [&](float* acc, const uint32_t* a, bool first, int s0, uint32_t par, bool last) {
            uint64_t bu = bd2;
            asm volatile("" : "+l"(bu));
            if (s0 < 4) par ^= 1;
            mbar_wait(fb + s0 * 8, par);
            bar_sync(8 + wg, 256);
            if (s0 == 4 && par == 1) PROF(39);
            wg_fence();
#pragma unroll
            for (int hf = 0; hf < 2; hf++) {
                const int s = s0 + hf;
                const uint32_t so = (s < 4 ? SM_RING + s * 16384 : ((s >> 1) & 1) * A_HALF + XSLOT_OFF + (s & 1) * 16384) >> 4;
                if (hf) { mbar_wait(fb + s * 8, par); wg_fence(); }
#pragma unroll
                for (int j = 0; j < 7; j++) {
                    const uint32_t* f = a + (hf * 7 + j) * 4;
                    wgmma_rs_n64<1>(acc, f[0], f[1], f[2], f[3], bu + (so + j * 128), !(first && hf == 0 && j == 0));
                }
            }
            wg_commit();
            if (s0 == 4 && par == 1) PROF(63);
            if (!(last && wg == 1)) asm volatile("bar.arrive %0, 256;" ::"r"(9 - wg) : "memory");
            wg_wait<0>();
            if (t == 0) { mbar_arrive(eb + s0 * 8); mbar_arrive(eb + s0 * 8 + 8); }
        };
#pragma unroll 1
        for (int ip = 0; ip < 2; ip++) {
            load_gb(1);
            unit(o[0], hh, true, 0, ip, false);
            if (ip) epilogue(o[1], 1);
            PROF(50 + 4 * ip);
            unit(o[1], hh, true, 2, ip, false);
            if (ip == 0) {
                mbar_wait(bars + 8 * (B_RECV + wg), 0);
#pragma unroll
                for (int i = 0; i < 14; i++) {
                    const uint4 v = lds128(sb + wg * A_HALF + RECV_OFF + t * 16 + i * 2048);
                    hh[56 + 4 * i] = v.x; hh[56 + 4 * i + 1] = v.y; hh[56 + 4 * i + 2] = v.z; hh[56 + 4 * i + 3] = v.w;
                }
                mbar_wait(bars + 8 * (B_DEAD + wg), 0);
            }
            PROF(51 + 4 * ip);
            load_gb(2 * ip);
            unit(o[0], hh + 56, false, 4, ip, false);
            epilogue(o[0], 2 * ip);
            PROF(52 + 4 * ip);
            unit(o[1], hh + 56, false, 6, ip, false);
            PROF(53 + 4 * ip);
        }
        load_gb(3);
        unit(o[0], hh, true, 0, 0, false);
        epilogue(o[1], 3);
        PROF(58);
        load_gb(4);
        unit(o[0], hh + 56, false, 2, 0, true);
        PROF(59);
        epilogue(o[0], 4);
        PROF(12);
        PROF(13);
        PROFG(15);
        PROF_DUMP;
    }
}

typedef CUresult (*EncodeFn)(CUtensorMap*, CUtensorMapDataType, cuuint32_t, void*, const cuuint64_t*, const cuuint64_t*, const cuuint32_t*,
                             const cuuint32_t*, CUtensorMapInterleave, CUtensorMapSwizzle, CUtensorMapL2promotion, CUtensorMapFloatOOBfill);

void encode(EncodeFn fn, CUtensorMap* m, const void* p, int rank, const cuuint64_t* dims, const cuuint64_t* strides, const cuuint32_t* box,
            CUtensorMapSwizzle sw, CUtensorMapL2promotion pr) {
    const cuuint32_t es[3] = {1, 1, 1};
    fn(m, CU_TENSOR_MAP_DATA_TYPE_BFLOAT16, rank, const_cast<void*>(p), dims, strides, box, es, CU_TENSOR_MAP_INTERLEAVE_NONE, sw, pr,
       CU_TENSOR_MAP_FLOAT_OOB_FILL_NONE);
}

}

extern "C" void kernel_launch(void* const* d_in, const int* in_sizes, int n_in, void* d_out, int out_size) {
    (void)in_sizes; (void)n_in; (void)out_size;
    static EncodeFn fn = nullptr;
    static void* x2pT = nullptr;
    static void* x2T = nullptr;
    static void* xT = nullptr;
    static void* st1 = nullptr;
    if (!fn) {
        void* f = nullptr;
        cudaDriverEntryPointQueryResult qr;
        cudaGetDriverEntryPoint("cuTensorMapEncodeTiled", &f, cudaEnableDefault, &qr);
        fn = (EncodeFn)f;
        cudaGetSymbolAddress(&x2pT, g_x2pT);
        cudaGetSymbolAddress(&x2T, g_x2T);
        cudaGetSymbolAddress(&xT, g_xT);
        cudaGetSymbolAddress(&st1, g_stats1);
        cudaFuncSetAttribute(fused_kernel, cudaFuncAttributeMaxDynamicSharedMemorySize, SM_TOTAL);
    }
    Params P;
    P.x = (const __nv_bfloat16*)d_in[0]; P.logA = (const __nv_bfloat16*)d_in[1]; P.Aim = (const __nv_bfloat16*)d_in[2];
    P.Cre = (const __nv_bfloat16*)d_in[3]; P.Cim = (const __nv_bfloat16*)d_in[4]; P.logdt = (const __nv_bfloat16*)d_in[5];
    P.Dskip = (const __nv_bfloat16*)d_in[6]; P.wg = (const __nv_bfloat16*)d_in[8]; P.wu = (const __nv_bfloat16*)d_in[9];
    P.wd = (const __nv_bfloat16*)d_in[10]; P.c = (const __nv_bfloat16*)d_in[11]; P.wmod = (const __nv_bfloat16*)d_in[12];
    P.out = (__nv_bfloat16*)d_out;

    CUtensorMap m_w1, m_g4, m_u4, m_g3, m_u3, m_wd, m_a, m_out, m_gs, m_us, m_t, m_wm, m_o3, m_x3, m_xs, m_st;
    {
        const cuuint64_t dims[2] = {D_, L_}, str[1] = {D_ * 2};
        const cuuint32_t boxo[2] = {64, 64};

        encode(fn, &m_out, P.out, 2, dims, str, boxo, CU_TENSOR_MAP_SWIZZLE_128B, CU_TENSOR_MAP_L2_PROMOTION_NONE);
    }
    {
        const cuuint64_t dims[3] = {32, D_, F_ / 32}, str[2] = {F_ * 2, 64};
        const cuuint32_t box4[3] = {32, 32, 4}, box3[3] = {32, 32, 3};
        encode(fn, &m_g4, P.wg, 3, dims, str, box4, CU_TENSOR_MAP_SWIZZLE_64B, CU_TENSOR_MAP_L2_PROMOTION_L2_128B);
        encode(fn, &m_u4, P.wu, 3, dims, str, box4, CU_TENSOR_MAP_SWIZZLE_64B, CU_TENSOR_MAP_L2_PROMOTION_L2_128B);
        encode(fn, &m_g3, P.wg, 3, dims, str, box3, CU_TENSOR_MAP_SWIZZLE_64B, CU_TENSOR_MAP_L2_PROMOTION_L2_128B);
        encode(fn, &m_u3, P.wu, 3, dims, str, box3, CU_TENSOR_MAP_SWIZZLE_64B, CU_TENSOR_MAP_L2_PROMOTION_L2_128B);
    }
    {
        const cuuint64_t dims[2] = {D_, F_}, str[1] = {D_ * 2};
        const cuuint32_t box[2] = {64, 112};
        encode(fn, &m_wd, P.wd, 2, dims, str, box, CU_TENSOR_MAP_SWIZZLE_128B, CU_TENSOR_MAP_L2_PROMOTION_L2_128B);
    }
    {
        const cuuint64_t dims[2] = {L_, D_}, str[1] = {L_ * 2};
        const cuuint32_t box[2] = {64, 64};
        encode(fn, &m_a, x2pT, 2, dims, str, box, CU_TENSOR_MAP_SWIZZLE_128B, CU_TENSOR_MAP_L2_PROMOTION_L2_128B);
        const cuuint32_t boxt[2] = {16, 128};
        encode(fn, &m_t, x2T, 2, dims, str, boxt, CU_TENSOR_MAP_SWIZZLE_32B, CU_TENSOR_MAP_L2_PROMOTION_NONE);
        const cuuint64_t dimo[3] = {64, L_, 10}, stro[2] = {D_ * 2, 128};
        const cuuint32_t boxo[3] = {64, 16, 10};
        encode(fn, &m_o3, P.out, 3, dimo, stro, boxo, CU_TENSOR_MAP_SWIZZLE_128B, CU_TENSOR_MAP_L2_PROMOTION_NONE);
        encode(fn, &m_x3, P.x, 3, dimo, stro, boxo, CU_TENSOR_MAP_SWIZZLE_128B, CU_TENSOR_MAP_L2_PROMOTION_L2_256B);
        const cuuint64_t dimx[3] = {L_, 128, 5}, strx[2] = {L_ * 2, 128 * L_ * 2};
        const cuuint32_t boxx[3] = {16, 128, 5};
        encode(fn, &m_xs, xT, 3, dimx, strx, boxx, CU_TENSOR_MAP_SWIZZLE_32B, CU_TENSOR_MAP_L2_PROMOTION_NONE);
        const cuuint64_t dimst[2] = {64, 128}, strst[1] = {128};
        const cuuint32_t boxst[2] = {64, 128};
        encode(fn, &m_st, st1, 2, dimst, strst, boxst, CU_TENSOR_MAP_SWIZZLE_128B, CU_TENSOR_MAP_L2_PROMOTION_NONE);
    }
    {
        const cuuint64_t dims[3] = {F_, 128, 5}, str[2] = {F_ * 2, 128 * F_ * 2};
        const cuuint32_t box[3] = {32, 128, 5};
        encode(fn, &m_gs, P.wg, 3, dims, str, box, CU_TENSOR_MAP_SWIZZLE_64B, CU_TENSOR_MAP_L2_PROMOTION_L2_256B);
        encode(fn, &m_us, P.wu, 3, dims, str, box, CU_TENSOR_MAP_SWIZZLE_64B, CU_TENSOR_MAP_L2_PROMOTION_L2_256B);
        const cuuint64_t dimw[3] = {6 * D_, 128, 5}, strw[2] = {6 * D_ * 2, 128 * 6 * D_ * 2};
        encode(fn, &m_wm, P.wmod, 3, dimw, strw, box, CU_TENSOR_MAP_SWIZZLE_64B, CU_TENSOR_MAP_L2_PROMOTION_L2_256B);
        const cuuint64_t dim1[2] = {6 * D_, D_};
        const cuuint32_t box1[2] = {32, 224};
        encode(fn, &m_w1, P.wmod, 2, dim1, strw, box1, CU_TENSOR_MAP_SWIZZLE_64B, CU_TENSOR_MAP_L2_PROMOTION_L2_256B);
    }
    fused_kernel<<<NCTA, 384, SM_TOTAL>>>(P, m_w1, m_g4, m_u4, m_g3, m_u3, m_wd, m_a, m_out, m_gs, m_us, m_t, m_wm, m_o3, m_x3, m_xs, m_st);
}
```
